```python
import torch

def _softmax(x, axis=-1):
    return torch.softmax(x, dim=axis)
def _gelu(x):
    return torch.nn.functional.gelu(x, approximate="tanh")
def _silu(x):
    return torch.nn.functional.silu(x)
def _sigmoid(x):
    return torch.sigmoid(x)
def _layernorm(x, axis=-1, eps=1e-5):
    m = x.mean(dim=axis, keepdim=True)
    v = x.var(dim=axis, keepdim=True, unbiased=False)
    return (x - m) / torch.sqrt(v + eps)
def _scatter_add(tgt, idx, src, axis=0):
    return tgt.clone().index_add_(axis, idx, src)
def _segment_sum(src, seg, n):
    out = torch.zeros((n,) + src.shape[1:], dtype=src.dtype)
    return out.index_add_(0, seg, src)
def _pad(x, pw):
    flat = tuple(v for pair in reversed(pw) for v in pair)
    return torch.nn.functional.pad(x, flat)

kernel_name = 'interleave_layers__mha_block__grouped_kv_mqa__prompt'

def setup_inputs():

    _w = (lambda a: (lambda t: t.to(torch.bfloat16) if t.is_floating_point() else t)(torch.as_tensor(a)))
    def _A_setup():
        B, S, D, H = 1, 2048, 512, 32
        return {
            "x": _w((lambda *s: torch.randn(*s, dtype=torch.bfloat16) * 0.05)(B, S, D)),
            "wqkv": _w((lambda *s: torch.randn(*s, dtype=torch.bfloat16) * 0.05)(D, 3 * D)),
            "wo": _w((lambda *s: torch.randn(*s, dtype=torch.bfloat16) * 0.05)(D, D)),
        }
    _A_in = _A_setup()

    def _B_setup():
        B, S, D, H = 1, 2048, 512, 32
        Dh = D // H
        return {
            "x": _w((lambda *s: torch.randn(*s, dtype=torch.bfloat16) * 0.05)(B, S, D)),
            "wq": _w((lambda *s: torch.randn(*s, dtype=torch.bfloat16) * 0.1)(D, H * Dh)),
            "wk": _w((lambda *s: torch.randn(*s, dtype=torch.bfloat16) * 0.1)(D, Dh)),
            "wv": _w((lambda *s: torch.randn(*s, dtype=torch.bfloat16) * 0.05)(D, Dh)),
            "wo": _w((lambda *s: torch.randn(*s, dtype=torch.bfloat16) * 0.05)(H * Dh, D)),
        }
    _B_in = _B_setup()

    return {
        "A_x": _A_in["x"],
        "A_wqkv": _A_in["wqkv"],
        "A_wo": _A_in["wo"],
        "B_x": _B_in["x"],
        "B_wq": _B_in["wq"],
        "B_wk": _B_in["wk"],
        "B_wv": _B_in["wv"],
        "B_wo": _B_in["wo"],
    }

def reference(A_x, A_wqkv, A_wo, B_x, B_wq, B_wk, B_wv, B_wo):
    def _A_ref(x, wqkv, wo):
        B, S, D = x.shape
        H = 32
        Dh = D // H
        qkv = (lambda x, *d: x.permute(*d))((x @ wqkv).reshape(B, S, 3, H, Dh), 2, 0, 3, 1, 4)
        q, k, v = qkv[0], qkv[1], qkv[2]
        scores = torch.einsum("bhqd,bhkd->bhqk", q, k) * (Dh ** -0.5)
        p = _softmax(scores, axis=-1)
        o = torch.einsum("bhqk,bhkd->bhqd", p, v)
        return (lambda x, *d: x.permute(*d))(o, 0, 2, 1, 3).reshape(B, S, D) @ wo

    def _B_ref(x, wq, wk, wv, wo):
        B, S, D = x.shape
        H = 32
        Dh = D // H
        q = (lambda x, *d: x.permute(*d))((x @ wq).reshape(B, S, H, Dh), 0, 2, 1, 3)
        k = x @ wk
        v = x @ wv
        scores = torch.einsum("bhqd,bkd->bhqk", q, k) * (Dh ** -0.5)
        p = _softmax(scores, axis=-1)
        o = torch.einsum("bhqk,bkd->bhqd", p, v)
        return (lambda x, *d: x.permute(*d))(o, 0, 2, 1, 3).reshape(B, S, H * Dh) @ wo

    x = A_x
    x = x + _A_ref(_layernorm(x, axis=-1), A_wqkv, A_wo)
    x = x + _B_ref(_layernorm(x, axis=-1), B_wq, B_wk, B_wv, B_wo)
    x = x + _A_ref(_layernorm(x, axis=-1), A_wqkv, A_wo)
    x = x + _B_ref(_layernorm(x, axis=-1), B_wq, B_wk, B_wv, B_wo)
    return x
```

```cpp
#include <cuda_runtime.h>
#include <cuda_bf16.h>
#include <cuda_fp16.h>
#include <cuda.h>
#include <stdint.h>

namespace {

constexpr int NCTA = 128;
constexpr int PAGE = 8192;
constexpr int W0N = 2, X0N = 2, PACE = 4, XPACE = 2, PACEA = 1, PACEB = 3;
constexpr int REC = 10240;
constexpr int NM = 32, NP = 128 - NM;
__host__ __device__ constexpr int mufu_pos(int i) { return i * 16 / (NM / 8); }
__host__ __device__ constexpr int blk_pos(int b) {
    if (b < NM / 8) return mufu_pos(b);
    int p = b - NM / 8;
    for (int i = 0; i < NM / 8; i++) if (mufu_pos(i) <= p) p++;
    return p;
}
__host__ __device__ constexpr int pos_blk(int p) { for (int b = 0; b < 16; b++) if (blk_pos(b) == p) return b; return 0; }
constexpr int SM_MISC = 28 * PAGE;
constexpr int SM_CS = SM_MISC + 512;
constexpr int SM_MASK = SM_CS + 272 * 4;
constexpr int SM_FILL = SM_MASK + 16;
constexpr int SM_ONES = SM_FILL + 256;
constexpr int SM_TOTAL = SM_ONES + 128;
constexpr int B_FULLW = 0, B_FULLWKV = 8, B_STAT = 9, B_MASK = 11, B_FULLA = 13, B_FULLO = 21, B_FULLWO = 29, B_FULLKV = 30, B_QREADY = 38,
              B_QKVDONE = 39, B_OUTDONE = 41, B_EMPTYA = 43, B_QSM = 51,
              B_QY = 52;
constexpr int N_OUT = 1, N_QKV = 5, N_O = 8, N_E1 = 12, N_E2 = 13, N_QFREE = 14;
constexpr int C_X = 0, C_Q = 128, C_O = 320, C_COUNT = 448;

__device__ uint4 g_Q[32 * 32 * 128];
__device__ uint4 g_KV[33 * 16 * REC / 16];
__device__ uint4 g_O[32 * 8 * PAGE / 16];
__device__ uint4 g_X[32 * 8 * PAGE / 16];
__device__ float2 g_stats[2048 * 8];
__device__ uint32_t g_kmax[33 * 128 * 8], g_vmax[33 * 128 * 8];
__device__ uint32_t g_cnt[C_COUNT * 32];
__device__ uint32_t g_epoch[NCTA];

struct Params {
    CUtensorMap tmX, tmWqkv, tmWoA, tmWq, tmWoB, tmWk, tmWv;
    const __nv_bfloat16 *x, *wqkv, *woA, *wq, *wk, *wv, *woB;
    __nv_bfloat16* out;
};

__device__ __forceinline__ void qk_m_set(float* d, const uint32_t* a, uint64_t db) {
    asm volatile("wgmma.mma_async.sync.aligned.m64n32k16.f32.f16.f16 {%0, %1, %2, %3, %4, %5, %6, %7, %8, %9, %10, %11, %12, %13, %14, %15}, {%16, %17, %18, %19}, %20, 0, 1, 1, 0;"
        : "=f"(d[0]), "=f"(d[1]), "=f"(d[2]), "=f"(d[3]), "=f"(d[4]), "=f"(d[5]), "=f"(d[6]), "=f"(d[7]), "=f"(d[8]), "=f"(d[9]), "=f"(d[10]), "=f"(d[11]), "=f"(d[12]), "=f"(d[13]), "=f"(d[14]), "=f"(d[15])
        : "r"(a[0]), "r"(a[1]), "r"(a[2]), "r"(a[3]), "l"(db));
}
__device__ __forceinline__ void qk_p_acc(float* d, const uint32_t* a, uint64_t db) {
    asm volatile("wgmma.mma_async.sync.aligned.m64n96k16.f32.f16.f16 {%0, %1, %2, %3, %4, %5, %6, %7, %8, %9, %10, %11, %12, %13, %14, %15, %16, %17, %18, %19, %20, %21, %22, %23, %24, %25, %26, %27, %28, %29, %30, %31, %32, %33, %34, %35, %36, %37, %38, %39, %40, %41, %42, %43, %44, %45, %46, %47}, {%48, %49, %50, %51}, %52, 1, 1, 1, 0;"
        : "+f"(d[0]), "+f"(d[1]), "+f"(d[2]), "+f"(d[3]), "+f"(d[4]), "+f"(d[5]), "+f"(d[6]), "+f"(d[7]), "+f"(d[8]), "+f"(d[9]), "+f"(d[10]), "+f"(d[11]), "+f"(d[12]), "+f"(d[13]), "+f"(d[14]), "+f"(d[15]), "+f"(d[16]), "+f"(d[17]), "+f"(d[18]), "+f"(d[19]), "+f"(d[20]), "+f"(d[21]), "+f"(d[22]), "+f"(d[23]), "+f"(d[24]), "+f"(d[25]), "+f"(d[26]), "+f"(d[27]), "+f"(d[28]), "+f"(d[29]), "+f"(d[30]), "+f"(d[31]), "+f"(d[32]), "+f"(d[33]), "+f"(d[34]), "+f"(d[35]), "+f"(d[36]), "+f"(d[37]), "+f"(d[38]), "+f"(d[39]), "+f"(d[40]), "+f"(d[41]), "+f"(d[42]), "+f"(d[43]), "+f"(d[44]), "+f"(d[45]), "+f"(d[46]), "+f"(d[47])
        : "r"(a[0]), "r"(a[1]), "r"(a[2]), "r"(a[3]), "l"(db));
}
__device__ __forceinline__ void fill_p(float* d, uint64_t da, uint64_t db) {
    asm volatile("wgmma.mma_async.sync.aligned.m64n96k16.f32.f16.f16 {%0, %1, %2, %3, %4, %5, %6, %7, %8, %9, %10, %11, %12, %13, %14, %15, %16, %17, %18, %19, %20, %21, %22, %23, %24, %25, %26, %27, %28, %29, %30, %31, %32, %33, %34, %35, %36, %37, %38, %39, %40, %41, %42, %43, %44, %45, %46, %47}, %48, %49, 0, 1, 1, 0, 0;"
        : "=f"(d[0]), "=f"(d[1]), "=f"(d[2]), "=f"(d[3]), "=f"(d[4]), "=f"(d[5]), "=f"(d[6]), "=f"(d[7]), "=f"(d[8]), "=f"(d[9]), "=f"(d[10]), "=f"(d[11]), "=f"(d[12]), "=f"(d[13]), "=f"(d[14]), "=f"(d[15]), "=f"(d[16]), "=f"(d[17]), "=f"(d[18]), "=f"(d[19]), "=f"(d[20]), "=f"(d[21]), "=f"(d[22]), "=f"(d[23]), "=f"(d[24]), "=f"(d[25]), "=f"(d[26]), "=f"(d[27]), "=f"(d[28]), "=f"(d[29]), "=f"(d[30]), "=f"(d[31]), "=f"(d[32]), "=f"(d[33]), "=f"(d[34]), "=f"(d[35]), "=f"(d[36]), "=f"(d[37]), "=f"(d[38]), "=f"(d[39]), "=f"(d[40]), "=f"(d[41]), "=f"(d[42]), "=f"(d[43]), "=f"(d[44]), "=f"(d[45]), "=f"(d[46]), "=f"(d[47])
        : "l"(da), "l"(db));
}
__device__ __forceinline__ void pv_acc(float* d, const uint32_t* a, uint64_t db) {
    asm volatile("wgmma.mma_async.sync.aligned.m64n24k16.f32.bf16.bf16 {%0, %1, %2, %3, %4, %5, %6, %7, %8, %9, %10, %11}, {%12, %13, %14, %15}, %16, 1, 1, 1, 1;"
        : "+f"(d[0]), "+f"(d[1]), "+f"(d[2]), "+f"(d[3]), "+f"(d[4]), "+f"(d[5]), "+f"(d[6]), "+f"(d[7]), "+f"(d[8]), "+f"(d[9]), "+f"(d[10]), "+f"(d[11])
        : "r"(a[0]), "r"(a[1]), "r"(a[2]), "r"(a[3]), "l"(db));
}
__device__ __forceinline__ void pv_set(float* d, const uint32_t* a, uint64_t db) {
    asm volatile("wgmma.mma_async.sync.aligned.m64n24k16.f32.bf16.bf16 {%0, %1, %2, %3, %4, %5, %6, %7, %8, %9, %10, %11}, {%12, %13, %14, %15}, %16, 0, 1, 1, 1;"
        : "=f"(d[0]), "=f"(d[1]), "=f"(d[2]), "=f"(d[3]), "=f"(d[4]), "=f"(d[5]), "=f"(d[6]), "=f"(d[7]), "=f"(d[8]), "=f"(d[9]), "=f"(d[10]), "=f"(d[11])
        : "r"(a[0]), "r"(a[1]), "r"(a[2]), "r"(a[3]), "l"(db));
}
__device__ __forceinline__ void gemm96(float* d, uint64_t da, uint64_t db) {
    asm volatile("wgmma.mma_async.sync.aligned.m64n96k16.f32.bf16.bf16 {%0, %1, %2, %3, %4, %5, %6, %7, %8, %9, %10, %11, %12, %13, %14, %15, %16, %17, %18, %19, %20, %21, %22, %23, %24, %25, %26, %27, %28, %29, %30, %31, %32, %33, %34, %35, %36, %37, %38, %39, %40, %41, %42, %43, %44, %45, %46, %47}, %48, %49, 1, 1, 1, 0, 1;"
        : "+f"(d[0]), "+f"(d[1]), "+f"(d[2]), "+f"(d[3]), "+f"(d[4]), "+f"(d[5]), "+f"(d[6]), "+f"(d[7]), "+f"(d[8]), "+f"(d[9]), "+f"(d[10]), "+f"(d[11]), "+f"(d[12]), "+f"(d[13]), "+f"(d[14]), "+f"(d[15]), "+f"(d[16]), "+f"(d[17]), "+f"(d[18]), "+f"(d[19]), "+f"(d[20]), "+f"(d[21]), "+f"(d[22]), "+f"(d[23]), "+f"(d[24]), "+f"(d[25]), "+f"(d[26]), "+f"(d[27]), "+f"(d[28]), "+f"(d[29]), "+f"(d[30]), "+f"(d[31]), "+f"(d[32]), "+f"(d[33]), "+f"(d[34]), "+f"(d[35]), "+f"(d[36]), "+f"(d[37]), "+f"(d[38]), "+f"(d[39]), "+f"(d[40]), "+f"(d[41]), "+f"(d[42]), "+f"(d[43]), "+f"(d[44]), "+f"(d[45]), "+f"(d[46]), "+f"(d[47])
        : "l"(da), "l"(db));
}
__device__ __forceinline__ void gemm64(float* d, uint64_t da, uint64_t db) {
    asm volatile("wgmma.mma_async.sync.aligned.m64n64k16.f32.bf16.bf16 {%0, %1, %2, %3, %4, %5, %6, %7, %8, %9, %10, %11, %12, %13, %14, %15, %16, %17, %18, %19, %20, %21, %22, %23, %24, %25, %26, %27, %28, %29, %30, %31}, %32, %33, 1, 1, 1, 0, 1;"
        : "+f"(d[0]), "+f"(d[1]), "+f"(d[2]), "+f"(d[3]), "+f"(d[4]), "+f"(d[5]), "+f"(d[6]), "+f"(d[7]), "+f"(d[8]), "+f"(d[9]), "+f"(d[10]), "+f"(d[11]), "+f"(d[12]), "+f"(d[13]), "+f"(d[14]), "+f"(d[15]), "+f"(d[16]), "+f"(d[17]), "+f"(d[18]), "+f"(d[19]), "+f"(d[20]), "+f"(d[21]), "+f"(d[22]), "+f"(d[23]), "+f"(d[24]), "+f"(d[25]), "+f"(d[26]), "+f"(d[27]), "+f"(d[28]), "+f"(d[29]), "+f"(d[30]), "+f"(d[31])
        : "l"(da), "l"(db));
}
__device__ __forceinline__ void gemm16(float* d, uint64_t da, uint64_t db) {
    asm volatile("wgmma.mma_async.sync.aligned.m64n16k16.f32.bf16.bf16 {%0, %1, %2, %3, %4, %5, %6, %7}, %8, %9, 1, 1, 1, 0, 1;"
        : "+f"(d[0]), "+f"(d[1]), "+f"(d[2]), "+f"(d[3]), "+f"(d[4]), "+f"(d[5]), "+f"(d[6]), "+f"(d[7])
        : "l"(da), "l"(db));
}

__device__ __forceinline__ int tidx() { int t; asm volatile("mov.u32 %0, %%tid.x;" : "=r"(t)); return t; }
__device__ __forceinline__ void wg_fence() { asm volatile("wgmma.fence.sync.aligned;" ::: "memory"); }
__device__ __forceinline__ void wg_commit() { asm volatile("wgmma.commit_group.sync.aligned;" ::: "memory"); }
template <int N> __device__ __forceinline__ void wg_wait() { asm volatile("wgmma.wait_group.sync.aligned %0;" ::"n"(N) : "memory"); }
template <int N> __device__ __forceinline__ void fence_regs(float* r) {
#pragma unroll
    for (int i = 0; i < N; i++) asm volatile("" : "+f"(r[i])::"memory");
}
template <int N> __device__ __forceinline__ void zero_regs(float* r) {
#pragma unroll
    for (int i = 0; i < N; i++) r[i] = 0.f;
    fence_regs<N>(r);
}
template <int N> __device__ __forceinline__ void fence_regs(uint32_t* r) {
#pragma unroll
    for (int i = 0; i < N; i++) asm volatile("" : "+r"(r[i])::"memory");
}
__device__ __forceinline__ uint64_t mkdesc(uint32_t addr, uint32_t lbo, uint32_t sbo, uint32_t swz) {
    return (uint64_t)((addr & 0x3FFFF) >> 4) | ((uint64_t)(lbo >> 4) << 16) | ((uint64_t)(sbo >> 4) << 32) | ((uint64_t)swz << 62);
}
__device__ __forceinline__ void mbar_init(uint32_t bar, int cnt) { asm volatile("mbarrier.init.shared::cta.b64 [%0], %1;" ::"r"(bar), "r"(cnt) : "memory"); }
__device__ __forceinline__ void mbar_expect(uint32_t bar, uint32_t bytes) { asm volatile("mbarrier.arrive.expect_tx.shared::cta.b64 _, [%0], %1;" ::"r"(bar), "r"(bytes) : "memory"); }
__device__ __forceinline__ void mbar_arrive(uint32_t bar) { asm volatile("mbarrier.arrive.shared::cta.b64 _, [%0];" ::"r"(bar) : "memory"); }
__device__ __forceinline__ void mbar_wait(uint32_t bar, uint32_t parity) {
    asm volatile("{\n.reg .pred p;\n.reg .u32 n;\n"
                 "mbarrier.try_wait.parity.shared::cta.b64 p, [%0], %1;\n@p bra DONE_%=;\nmov.u32 n, 0;\n"
                 "WAIT_%=:\nmbarrier.try_wait.parity.shared::cta.b64 p, [%0], %1;\n@p bra DONE_%=;\n"
                 "add.u32 n, n, 1;\nsetp.lt.u32 p, n, 0x400000;\n@p bra WAIT_%=;\ntrap;\nDONE_%=:\n}" ::"r"(bar), "r"(parity) : "memory");
}
__device__ __forceinline__ void mbar_nap(uint32_t bar, uint32_t parity) {
    asm volatile("{\n.reg .pred p;\n.reg .u32 n;\nmov.u32 n, 0;\n"
                 "WAIT_%=:\nmbarrier.test_wait.parity.shared::cta.b64 p, [%0], %1;\n@p bra DONE_%=;\nnanosleep.u32 256;\n"
                 "add.u32 n, n, 1;\nsetp.lt.u32 p, n, 0x800000;\n@p bra WAIT_%=;\ntrap;\nDONE_%=:\n}" ::"r"(bar), "r"(parity) : "memory");
}
__device__ __forceinline__ bool elect() {
    uint32_t r;
    asm volatile("{\n.reg .pred p;\nelect.sync _|p, 0xffffffff;\nselp.u32 %0, 1, 0, p;\n}" : "=r"(r));
    return r;
}
__device__ __forceinline__ void nb_arrive(int id, int n) { asm volatile("bar.arrive %0, %1;" ::"r"(id), "r"(n) : "memory"); }
__device__ __forceinline__ void nb_sync(int id, int n) { asm volatile("bar.sync %0, %1;" ::"r"(id), "r"(n) : "memory"); }
__device__ __forceinline__ void warp_arrive(uint32_t bar) { __syncwarp(); if (elect()) mbar_arrive(bar); }
__device__ __forceinline__ void bulk_g2s(uint32_t dst, const void* src, uint32_t bytes, uint32_t bar) {
    asm volatile("cp.async.bulk.shared::cluster.global.mbarrier::complete_tx::bytes [%0], [%1], %2, [%3];" ::"r"(dst), "l"(src), "r"(bytes), "r"(bar) : "memory");
}
__device__ __forceinline__ void tma2d(uint32_t dst, const CUtensorMap* tm, int c0, int c1, uint32_t bar) {
    asm volatile("cp.async.bulk.tensor.2d.shared::cluster.global.mbarrier::complete_tx::bytes [%0], [%1, {%3, %4}], [%2];" ::"r"(dst), "l"(tm), "r"(bar), "r"(c0), "r"(c1) : "memory");
}
__device__ __forceinline__ void fence_async() { asm volatile("fence.proxy.async.global;" ::: "memory"); }
__device__ __forceinline__ void poll(int idx, uint32_t target, bool sleepy) {
    const uint32_t* p = &g_cnt[idx * 32];
    for (int it = 0;; it++) {
        uint32_t v;
        asm volatile("ld.acquire.gpu.global.u32 %0, [%1];" : "=r"(v) : "l"(p) : "memory");
        if (__all_sync(~0u, (int)(v - target) >= 0)) break;
        if (it > (1 << 22)) __trap();
        if (sleepy) __nanosleep(100);
    }
}
__device__ __forceinline__ void publish(int idx) { asm volatile("red.release.gpu.global.add.u32 [%0], 1;" ::"l"(&g_cnt[idx * 32]) : "memory"); }
__device__ __forceinline__ void bump(int idx) { asm volatile("red.relaxed.gpu.global.add.u32 [%0], 1;" ::"l"(&g_cnt[idx * 32]) : "memory"); }
__device__ __forceinline__ uint32_t pack_bf16(float lo, float hi) { uint32_t r; asm("cvt.rn.bf16x2.f32 %0, %1, %2;" : "=r"(r) : "f"(hi), "f"(lo)); return r; }
__device__ __forceinline__ uint32_t pack_f16(float lo, float hi) { uint32_t r; asm("cvt.rn.f16x2.f32 %0, %1, %2;" : "=r"(r) : "f"(hi), "f"(lo)); return r; }
__device__ __forceinline__ float bf_lo(uint32_t v) { return __uint_as_float(v << 16); }
__device__ __forceinline__ float bf_hi(uint32_t v) { return __uint_as_float(v & 0xFFFF0000u); }
__device__ __forceinline__ float ex2(float x) { float r; asm("ex2.approx.ftz.f32 %0, %1;" : "=f"(r) : "f"(x)); return r; }
__device__ __forceinline__ uint32_t hfma2(uint32_t a, uint32_t b, uint32_t c) { uint32_t r; asm("fma.rn.bf16x2 %0, %1, %2, %3;" : "=r"(r) : "r"(a), "r"(b), "r"(c)); return r; }
__device__ __forceinline__ float quad_sum(float v) { v += __shfl_xor_sync(~0u, v, 1); return v + __shfl_xor_sync(~0u, v, 2); }
__device__ __forceinline__ float quad_max(float v) { v = fmaxf(v, __shfl_xor_sync(~0u, v, 1)); return fmaxf(v, __shfl_xor_sync(~0u, v, 2)); }

struct Buf { float sm[NM / 2]; float sp[NP / 2]; uint32_t p[(NM + NP) / 4]; };

__device__ __forceinline__ uint32_t exp_poly(float y0, float y1) {
    uint32_t z;
    asm("prmt.b32 %0, %1, %2, 0x6521;" : "=r"(z) : "r"(__float_as_uint(y0)), "r"(__float_as_uint(y1)));
    const uint32_t d = hfma2(z, 0xFE7BFE7Bu - z, 0x3F053F05u);
    return hfma2(z, d, z);
}
__device__ __forceinline__ void lds_q(uint32_t* q, uint32_t qaddr) {
    asm volatile("ld.shared.v4.u32 {%0, %1, %2, %3}, [%4];" : "=r"(q[0]), "=r"(q[1]), "=r"(q[2]), "=r"(q[3]) : "r"(qaddr) : "memory");
    fence_regs<4>(q);
}
__device__ __forceinline__ void first_qk(Buf& t, const uint32_t* q, uint32_t sbase, int rec) {
    const uint64_t d = mkdesc(sbase + rec * REC, 128, 256, 0);
    qk_m_set(t.sm, q, d);
    fill_p(t.sp, mkdesc(sbase + SM_FILL, 128, 0, 0), mkdesc(sbase + rec * REC + 4096 + 512, 128, 0, 0));
    qk_p_acc(t.sp, q, d + NM * 2);
}
template <int MODE>
__device__ __forceinline__ void fast_step(Buf& t, Buf& u, uint32_t* q, float* o, uint64_t d, uint32_t qnext, uint32_t sbase) {
#pragma unroll
    for (int s = 0; s < 4; s++) {
#pragma unroll
        for (int i = 8 * s; i < 8 * s + 8; i++) {
            constexpr int MB = NM / 8;
            const int blk = pos_blk(i >> 1), e = 4 * (blk < MB ? blk : blk - MB) + 2 * (i & 1);
            t.p[i] = blk < MB ? pack_bf16(ex2(t.sm[e]), ex2(t.sm[e + 1])) : exp_poly(t.sp[e], t.sp[e + 1]);
        }
        if (s & 1) {
            fence_regs<16>(&t.p[8 * s - 8]);
            wg_fence();
            if (s == 3 && MODE == 1) first_qk(t, q, sbase, 0);
#pragma unroll
            for (int k = 2 * s - 2; k < 2 * s + 2; k++) { if (k == 0 && MODE == 3) pv_set(o, t.p, d + 256); else pv_acc(o, &t.p[4 * k], d + 256 + k * 48); }
            if (s == 3 && MODE % 3 == 0) { qk_m_set(t.sm, q, d + 2 * (REC / 16)); qk_p_acc(t.sp, q, d + 2 * (REC / 16) + NM * 2); }
            if (s == 3 && MODE == 2) { wg_commit(); first_qk(t, q, sbase, 1); }
            if (s == 3 || MODE == 1) wg_commit();
            if (s == 1 && MODE == 1) { wg_wait<1>(); lds_q(q, qnext); }
            if (s == 3) { wg_wait<1>(); fence_regs<NM / 2>(u.sm); fence_regs<NP / 2>(u.sp); }
        }
    }
}
template <bool F16> __device__ __forceinline__ void hmma(float* d, const uint32_t* a, uint32_t b0, uint32_t b1) {
    if (F16) asm("mma.sync.aligned.m16n8k16.row.col.f32.f16.f16.f32 {%0,%1,%2,%3}, {%4,%5,%6,%7}, {%8,%9}, {%0,%1,%2,%3};"
                 : "+f"(d[0]), "+f"(d[1]), "+f"(d[2]), "+f"(d[3]) : "r"(a[0]), "r"(a[1]), "r"(a[2]), "r"(a[3]), "r"(b0), "r"(b1));
    else asm("mma.sync.aligned.m16n8k16.row.col.f32.bf16.bf16.f32 {%0,%1,%2,%3}, {%4,%5,%6,%7}, {%8,%9}, {%0,%1,%2,%3};"
             : "+f"(d[0]), "+f"(d[1]), "+f"(d[2]), "+f"(d[3]) : "r"(a[0]), "r"(a[1]), "r"(a[2]), "r"(a[3]), "r"(b0), "r"(b1));
}
__device__ __forceinline__ void slow_pass(const uint32_t* q, float* o, uint32_t sbase) {
    float sc[64];
#pragma unroll
    for (int i = 0; i < 12; i++) o[i] = 0.f;
#pragma unroll
    for (int i = 0; i < 64; i++) sc[i] = 0.f;
    float m0 = -INFINITY, m1 = -INFINITY;
#pragma unroll 1
    for (int st = 0; st < 16; st++) {
        const uint32_t rec = sbase + (tidx() & 31) * 16 + (((2 * st) & 15) + (st >> 3)) * REC;
#pragma unroll
        for (int i = 0; i < 64; i++) sc[i] = (i < NM / 2 || st == 8) ? 0.f : sc[i];
        float a0 = m0, a1 = m1;
#pragma unroll
        for (int b2 = 0; b2 < 8; b2++) {
            uint32_t k[4];
            asm volatile("ldmatrix.sync.aligned.m8n8.x4.shared.b16 {%0,%1,%2,%3}, [%4];" : "=r"(k[0]), "=r"(k[1]), "=r"(k[2]), "=r"(k[3]) : "r"(rec + b2 * 512) : "memory");
#pragma unroll
            for (int u = 0; u < 2; u++) {
                float* d = sc + 8 * b2 + 4 * u;
                hmma<true>(d, q, k[2 * u], k[2 * u + 1]);
                const float f = 2 * b2 + u < NM / 8 ? 1.f : 0.5f;
                a0 = fmaxf(a0, f * fmaxf(d[0], d[1])); a1 = fmaxf(a1, f * fmaxf(d[2], d[3]));
            }
        }
        a0 = quad_max(a0); a1 = quad_max(a1);
        const float s0 = ex2(m0 - a0), s1 = ex2(m1 - a1);
        m0 = a0; m1 = a1;
#pragma unroll
        for (int i = 0; i < 3; i++) { o[4 * i] *= s0; o[4 * i + 1] *= s0; o[4 * i + 2] *= s1; o[4 * i + 3] *= s1; }
#pragma unroll
        for (int c = 0; c < 8; c++) {
            uint32_t v[4], p[4];
            asm volatile("ldmatrix.sync.aligned.m8n8.x4.trans.shared.b16 {%0,%1,%2,%3}, [%4];" : "=r"(v[0]), "=r"(v[1]), "=r"(v[2]), "=r"(v[3]) : "r"(rec + 4096 + c * 768) : "memory");
#pragma unroll
            for (int i = 0; i < 4; i++) {
                const int blk = pos_blk(2 * c + (i >> 1));
                const float f = blk < NM / 8 ? 1.f : 0.5f, m = (i & 1) ? m1 : m0, *d = sc + 4 * blk + 2 * (i & 1);
                p[i] = pack_bf16(ex2(fmaf(d[0], f, -m)), ex2(fmaf(d[1], f, -m)));
            }
            hmma<false>(o, p, v[0], v[1]); hmma<false>(o + 4, p, v[2], v[3]); hmma<false>(o + 8, p, 0x3F803F80u, 0x3F803F80u);
        }
    }
}
__device__ __forceinline__ uint32_t unsafe_mask(int par, int w, uint32_t sbase) {
    const int lane = tidx() & 31, hk = par ? 32 : blockIdx.x >> 2;
    uint32_t km = 0, vm = 0;
#pragma unroll
    for (int i = 0; i < 4; i++) { km = max(km, __ldcg(&g_kmax[(hk * 128 + i * 32 + lane) * 8])); vm = max(vm, __ldcg(&g_vmax[(hk * 128 + i * 32 + lane) * 8])); }
    const float k2 = __uint_as_float(__reduce_max_sync(~0u, km)), lv = __log2f(__uint_as_float(__reduce_max_sync(~0u, vm)));
    const float bm = fminf(fminf(116.f - lv, 115.f), 106.f + lv);
    const float lim = (bm > 0.f && k2 <= 6.4e7f) ? 0.98f * bm * bm / k2 : -1.f;
    uint32_t mask = 0;
#pragma unroll 1
    for (int p = 0; p < 4; p++) {
        __half2 n0 = __float2half2_rn(0.f), n1 = n0;
#pragma unroll
        for (int i = 0; i < 4; i++) {
            uint4 q;
            asm volatile("ld.shared.v4.u32 {%0, %1, %2, %3}, [%4];" : "=r"(q.x), "=r"(q.y), "=r"(q.z), "=r"(q.w) : "r"(sbase + 26 * PAGE + (2 * p + w) * 2048 + lane * 64 + i * 16) : "memory");
            n0 = __hfma2(*(__half2*)&q.x, *(__half2*)&q.x, __hfma2(*(__half2*)&q.z, *(__half2*)&q.z, n0));
            n1 = __hfma2(*(__half2*)&q.y, *(__half2*)&q.y, __hfma2(*(__half2*)&q.w, *(__half2*)&q.w, n1));
        }
        const float2 f0 = __half22float2(n0), f1 = __half22float2(n1);
        if (__any_sync(~0u, !(f0.x + f0.y <= lim) || !(f1.x + f1.y <= lim))) mask |= 1u << p;
    }
    return mask;
}
__device__ __forceinline__ int unit_tile(int par, int p, int w) { return (p >> 1) * 16 + (par ? blockIdx.x >> 3 : 4 * (blockIdx.x & 3) + 2 * (p & 1) + w); }
__device__ __forceinline__ int unit_head(int par, int p, int w) { return par ? 4 * (blockIdx.x & 7) + 2 * (p & 1) + w : blockIdx.x >> 2; }
__device__ __forceinline__ uint4 pack_o(const float* o) {
    const int lane = tidx() & 31;
    const float r0 = __fdividef(1.f, __shfl_sync(~0u, o[8], lane & ~3)), r1 = __fdividef(1.f, __shfl_sync(~0u, o[10], lane & ~3));
    return make_uint4(pack_bf16(o[0] * r0, o[1] * r0), pack_bf16(o[4] * r0, o[5] * r0), pack_bf16(o[2] * r1, o[3] * r1), pack_bf16(o[6] * r1, o[7] * r1));
}
__device__ __forceinline__ void store_o(uint4 v, int T, int h, int on) {
    const int tid = tidx() & 127;
    uint32_t* ob = (uint32_t*)g_O + (T * 32 + h) * 512 + (tid >> 5) * 128 + (tid & 31);
    asm volatile("{\n.reg .pred p;\nsetp.ne.u32 p, %5, 0;\n@p st.global.u32 [%0], %1;\n@p st.global.u32 [%0 + 128], %2;\n@p st.global.u32 [%0 + 256], %3;\n@p st.global.u32 [%0 + 384], %4;\n}"
                 ::"l"(ob), "r"(v.x), "r"(v.y), "r"(v.z), "r"(v.w), "r"(on) : "memory");
}
__device__ __forceinline__ uint32_t mbar_test(uint32_t bar, uint32_t parity) {
    uint32_t ok;
    asm volatile("{\n.reg .pred p;\nmbarrier.test_wait.parity.shared::cta.b64 p, [%1], %2;\nselp.u32 %0, 1, 0, p;\n}" : "=r"(ok) : "r"(bar), "r"(parity) : "memory");
    return ok;
}
__device__ __forceinline__ void nb_arrive_if(bool on, int id, int n) {
    asm volatile("{\n.reg .pred p;\nsetp.ne.u32 p, %0, 0;\n@p bar.arrive %1, %2;\n}" ::"r"((int)on), "r"(id), "r"(n) : "memory");
}
__device__ __forceinline__ void attention(int L, int w, uint32_t sbase) {
    const int par = L & 1, tid = tidx() & 127;
    const uint32_t bars = sbase + SM_MISC;
    const uint32_t qaddr = sbase + 26 * PAGE + w * 2048 + tid * 16;
    Buf a, b;
    uint32_t q[4];
    float o[12];
    zero_regs<12>(o);
    if (par) mbar_wait(bars + 8 * B_QSM, L >> 1);
    mbar_wait(bars + 8 * B_QREADY, par);
    lds_q(q, qaddr);
    wg_fence();
    first_qk(a, q, sbase, 0); wg_commit();
    mbar_wait(bars + 8 * B_FULLKV, par);
    wg_fence();
    first_qk(b, q, sbase, 1); wg_commit();
    mbar_wait(bars + 8 * (B_FULLKV + 1), par);
    wg_wait<1>();
    fence_regs<NM / 2>(a.sm); fence_regs<NP / 2>(a.sp);
    uint32_t mask = 0;
#pragma unroll 1
    for (int p = 0; p < 4; p++) {
        uint64_t d = mkdesc(sbase, 128, 256, 0);
        uint32_t bar = bars + 8 * (B_FULLKV + 2);
        {
            const uint32_t ok = mbar_test(bar, par);
            store_o(pack_o(o), unit_tile(par, p - 1, w), unit_head(par, p - 1, w), p);
            fast_step<3>(a, b, q, o, d, 0, 0);
            nb_arrive_if(p && !mask, N_O + p - 1, 288);
            nb_arrive_if(p == 3 && !mask, N_QFREE, 288);
            fast_step<0>(b, a, q, o, d + REC / 16, 0, 0);
            if (!ok) mbar_wait(bar, par);
        }
#pragma unroll 3
        for (int it = 1; it < 7; it++) {
            d += 2 * (REC / 16);
            bar += 8;
            const uint32_t ok = mbar_test(bar, par);
            fast_step<0>(a, b, q, o, d, 0, 0);
            fast_step<0>(b, a, q, o, d + REC / 16, 0, 0);
            nb_arrive_if(it == 4 && p == 3 && !mask, N_E1, 288);
            if (!ok && it < 6) mbar_wait(bar, par);
        }
        d += 2 * (REC / 16);
        fast_step<1>(a, b, q, o, d, qaddr + ((p + 1) & 3) * 4096, sbase);
        fast_step<2>(b, a, q, o, d + REC / 16, 0, sbase);
        fence_regs<12>(o);
        if (p == 0) {
            uint32_t m0, m1;
            mbar_wait(bars + 8 * B_MASK, par);
            mbar_wait(bars + 8 * (B_MASK + 1), par);
            asm volatile("ld.shared.v2.u32 {%0, %1}, [%2];" : "=r"(m0), "=r"(m1) : "r"(sbase + SM_MASK) : "memory");
            mask = __shfl_sync(~0u, w ? m1 | m0 << 4 : m0 | m1 << 4, 0);
        }
    }
    nb_arrive_if(!mask, N_E2, 320);
    store_o(pack_o(o), unit_tile(par, 3, w), unit_head(par, 3, w), 1);
    if (!mask) nb_arrive(N_O + 3, 288);
    wg_wait<0>();
    fence_regs<NM / 2>(b.sm); fence_regs<NP / 2>(b.sp);
    if (mask) {
#pragma unroll 1
        for (int p = 0; p < 4; p++) {
            if ((mask >> p) & 1) {
                float o2[12];
                uint32_t q2[4];
                lds_q(q2, qaddr + p * 4096);
                slow_pass(q2, o2, sbase);
                store_o(pack_o(o2), unit_tile(par, p, w), unit_head(par, p, w), 1);
            }
            nb_arrive(N_O + p, 288);
        }
        nb_arrive(N_QFREE, 288);
        nb_arrive(N_E1, 288);
        nb_arrive(N_E2, 320);
    }
}

__device__ __forceinline__ void block_stats(const uint32_t* xv, int T, int c) {
    const int tid = tidx() & 127, lane = tid & 31, warp = tid >> 5, g = lane >> 2, t = lane & 3;
    float s0 = 0.f, s1 = 0.f;
#pragma unroll
    for (int i = 0; i < 8; i++) { s0 += bf_lo(xv[2 * i]) + bf_hi(xv[2 * i]); s1 += bf_lo(xv[2 * i + 1]) + bf_hi(xv[2 * i + 1]); }
    s0 = quad_sum(s0) * (1.f / 64); s1 = quad_sum(s1) * (1.f / 64);
    float v0 = 0.f, v1 = 0.f;
#pragma unroll
    for (int i = 0; i < 8; i++) {
        float a = bf_lo(xv[2 * i]) - s0, b = bf_hi(xv[2 * i]) - s0, e = bf_lo(xv[2 * i + 1]) - s1, f = bf_hi(xv[2 * i + 1]) - s1;
        v0 += a * a + b * b; v1 += e * e + f * f;
    }
    v0 = quad_sum(v0); v1 = quad_sum(v1);
    if (t < 2) g_stats[(T * 8 + c) * 64 + warp * 16 + g + t * 8] = t ? make_float2(s1, v1) : make_float2(s0, v0);
}
__device__ __forceinline__ uint4 ld_stats(int T, int half) {
    const int tid = tidx() & 127;
    const float2* p = &g_stats[(T * 8 + 2 * (tid & 3)) * 64 + (tid >> 5) * 16 + ((tid & 31) >> 2) + 8 * half];
    const float2 a = __ldcg(p), b = __ldcg(p + 64);
    return make_uint4(__float_as_uint(a.x), __float_as_uint(a.y), __float_as_uint(b.x), __float_as_uint(b.y));
}
__device__ __forceinline__ void row_stats(uint4 u, float& mean, float& rstd) {
    float m0 = __uint_as_float(u.x), m1 = __uint_as_float(u.z);
    mean = quad_sum(m0 + m1) * 0.125f;
    float var = quad_sum(__uint_as_float(u.y) + __uint_as_float(u.w) + 64.f * ((m0 - mean) * (m0 - mean) + (m1 - mean) * (m1 - mean))) * (1.f / 512);
    rstd = rsqrtf(var + 1e-5f);
}
__device__ __forceinline__ uint32_t store_k(const float* y, int hk, int w, int r, uint32_t* link) {
    const int tid = tidx() & 127, lane = tid & 31, warp = tid >> 5, g = lane >> 2, t = lane & 3;
    const float n0 = y[0] * y[0] + y[1] * y[1] + y[4] * y[4] + y[5] * y[5], n1 = y[2] * y[2] + y[3] * y[3] + y[6] * y[6] + y[7] * y[7];
    float n = ((t & 1) ? n1 : n0) + __shfl_xor_sync(~0u, (t & 1) ? n0 : n1, 1);
    n += __shfl_xor_sync(~0u, n, 2);
    const bool poly = 2 * (r & 7) + (warp >> 1) >= NM / 8;
    const float sc = poly ? 2.f : 1.f;
    uint8_t* kb = (uint8_t*)g_KV + (size_t)(hk * 16 + 2 * (4 * w + (g & 3)) + (r >> 3)) * REC + (2 * (r & 7) + (warp >> 1)) * 256 + (4 * (warp & 1) + (g >> 2)) * 16 + t * 4;
#pragma unroll
    for (int i = 0; i < 4; i++) {
        uint32_t v = pack_f16(y[2 * i] * sc, y[2 * i + 1] * sc);
        uint32_t prev = __shfl_up_sync(~0u, v, 4);
        if ((g & 3) == 0) prev = link[i];
        link[i] = v;
        if (poly) { __half2 dl = __hsub2(*(__half2*)&v, *(__half2*)&prev); v = *(uint32_t*)&dl; }
        *(uint32_t*)(kb + (i >> 1) * 128 + (i & 1) * 32) = v;
    }
    return __float_as_uint(n) & 0x7FFFFFFFu;
}
__device__ __forceinline__ uint32_t store_v(const float* y, int hk, int w, int r) {
    const int tid = tidx() & 127, lane = tid & 31, warp = tid >> 5, g = lane >> 2, t = lane & 3;
    const int blk = 2 * (r & 7) + (warp >> 1), pos = blk_pos(blk);
    uint8_t* vb = (uint8_t*)g_KV + (size_t)(hk * 16 + 2 * (4 * w + (g & 3)) + (r >> 3)) * REC + 4096 + (pos >> 1) * 768 + (pos & 1) * 128 + (4 * (warp & 1) + (g >> 2)) * 16 + t * 4;
    uint32_t am = 0;
#pragma unroll
    for (int i = 0; i < 4; i++) {
        const uint32_t v = pack_bf16(y[2 * i], y[2 * i + 1]);
        *(uint32_t*)(vb + (i >> 1) * 256 + (i & 1) * 32) = v;
        am = __vmaxu2(am, v & 0x7FFF7FFFu);
    }
    return max(am << 16, am & 0xFFFF0000u);
}
__device__ __forceinline__ void store_max(uint32_t* dst, uint32_t v, int hk, int T) {
    v = __reduce_max_sync(~0u, v);
    if ((tidx() & 31) < 8) dst[(hk * 128 + T * 4 + ((tidx() >> 5) & 3)) * 8 + (tidx() & 7)] = v;
}
__device__ __forceinline__ void normalise(float* acc, const float2* c, float mu0, float mu1, float r0, float r1) {
#pragma unroll
    for (int i = 0; i < 2; i++) {
        acc[4 * i] = (acc[4 * i] - mu0 * c[i].x) * r0; acc[4 * i + 1] = (acc[4 * i + 1] - mu0 * c[i].y) * r0;
        acc[4 * i + 2] = (acc[4 * i + 2] - mu1 * c[i].x) * r1; acc[4 * i + 3] = (acc[4 * i + 3] - mu1 * c[i].y) * r1;
    }
}
template <int N> __device__ __forceinline__ void load_cs(float2* c, const float* cs) {
    const int t = tidx() & 3;
#pragma unroll
    for (int i = 0; i < N; i++) c[i] = *(const float2*)(cs + 8 * i + 2 * t);
}
constexpr float QSCALE = 0.25f * 1.4426950408889634f;
template <int N> __device__ __forceinline__ void put_cs(float* dst, const float* d) {
    const int tid = tidx() & 127;
    if (tid < 4) {
#pragma unroll
        for (int i = 0; i < N; i++) *(float2*)(dst + 8 * i + 2 * tid) = make_float2(d[4 * i], d[4 * i + 1]);
    }
}
template <bool KV> __device__ __forceinline__ void qkv_b_loop(float* acc, int L, int s, uint32_t sbase) {
    const uint32_t bars = sbase + SM_MISC;
#pragma unroll 1
    for (int k2 = 0; k2 < 4; k2++) {
        if (!KV) { mbar_wait(bars + 8 * (B_FULLW + 2 * k2), 1); mbar_wait(bars + 8 * (B_FULLW + 2 * k2 + 1), 1); }
        mbar_wait(bars + 8 * (B_FULLA + s * 4 + k2), L >> 1);
        const uint64_t da = mkdesc(sbase + (10 + 8 * s + 2 * k2) * PAGE, 128, 256, 0);
        const uint64_t db = KV ? mkdesc(sbase + 8 * PAGE + k2 * 4096, 16, 256, 3) : mkdesc(sbase + 2 * k2 * PAGE, PAGE, 1024, 1);
        wg_fence();
#pragma unroll
        for (int ks = 0; ks < 8; ks++) { if (KV) gemm16(acc, da + 128 * ks, db + 32 * ks); else gemm64(acc, da + 128 * ks, db + 128 * ks); }
        wg_commit();
    }
    wg_wait<0>();
    fence_regs<KV ? 8 : 32>(acc);
}
__device__ __forceinline__ void kv_extra(int L, uint32_t sbase, const float* cs) {
    const int r = blockIdx.x >> 3, c = blockIdx.x & 7;
    const uint32_t bars = sbase + SM_MISC;
    uint32_t link[4] = {0, 0, 0, 0};
    float2 cc[2];
    load_cs<2>(cc, cs + 256);
    mbar_wait(bars + 8 * B_FULLWKV, (L >> 1) & 1);
#pragma unroll 1
    for (int s = 0; s < 2; s++) {
        const int T = s * 16 + r;
        float ex[8], mu0, mu1, r0, r1;
        zero_regs<8>(ex);
        mbar_wait(bars + 8 * (B_STAT + s), 1);
        row_stats(ld_stats(T, 0), mu0, r0); row_stats(ld_stats(T, 1), mu1, r1);
        qkv_b_loop<true>(ex, L, s, sbase);
        if (s == 1) warp_arrive(bars + 8 * (B_QKVDONE + 1));
        normalise(ex, cc, mu0, mu1, r0, r1);
        if (c == 0) store_max(g_kmax, store_k(ex, 32, s, r, link), 32, T); else store_max(g_vmax, store_v(ex, 32, s, r), 32, T);
        nb_arrive(N_QKV + s, 160);
#pragma unroll
        for (int i = 0; i < 4; i++) link[i] = __shfl_down_sync(~0u, link[i], 12);
    }
}
__device__ __forceinline__ void pre_load(uint4* xv, int u, const __nv_bfloat16* x) {
    const int tid = tidx() & 127, row0 = (u * 16 + (blockIdx.x >> 3)) * 64 + (tid >> 5) * 16 + ((tid & 31) >> 3);
#pragma unroll
    for (int i = 0; i < 4; i++)
        asm volatile("ld.global.nc.v4.u32 {%0, %1, %2, %3}, [%4];" : "=r"(xv[i].x), "=r"(xv[i].y), "=r"(xv[i].z), "=r"(xv[i].w) : "l"((const uint4*)x + (row0 + 4 * i) * 64 + (blockIdx.x & 7) * 8 + (tid & 7)) : "memory");
}
__device__ __forceinline__ void pre_phase(const uint4* xv, int u) {
    const int tid = tidx() & 127, c = blockIdx.x & 7;
    const int row0 = (u * 16 + (blockIdx.x >> 3)) * 64 + (tid >> 5) * 16 + ((tid & 31) >> 3);
#pragma unroll
    for (int i = 0; i < 4; i++) {
        const float v[8] = {bf_lo(xv[i].x), bf_hi(xv[i].x), bf_lo(xv[i].y), bf_hi(xv[i].y), bf_lo(xv[i].z), bf_hi(xv[i].z), bf_lo(xv[i].w), bf_hi(xv[i].w)};
        float m = quad_sum(((v[0] + v[1]) + (v[2] + v[3])) + ((v[4] + v[5]) + (v[6] + v[7])));
        m = (m + __shfl_xor_sync(~0u, m, 4)) * (1.f / 64);
        float q = 0.f;
#pragma unroll
        for (int k = 0; k < 8; k++) q += (v[k] - m) * (v[k] - m);
        q = quad_sum(q);
        q += __shfl_xor_sync(~0u, q, 4);
        if ((tid & 7) == 0) g_stats[((row0 >> 6) * 8 + c) * 64 + (row0 & 63) + 4 * i] = make_float2(m, q);
    }
    nb_arrive(N_O, 288);
#pragma unroll
    for (int i = 0; i < 3; i++) {
        const int rr = i < 2 ? 2 * (blockIdx.x >> 4) + u : blockIdx.x >> 3, pos = blk_pos(2 * (rr & 7) + ((tid >> 3) & 1));
        uint8_t* o = (uint8_t*)g_KV + ((i < 2 ? 2 * (blockIdx.x & 15) + i : 32) * 16 + 2 * (tid >> 4) + (rr >> 3)) * REC + 4096 + (pos >> 1) * 768 + (pos & 1) * 128 + 512 + (tid & 7) * 16;
        if (i < 2 || ((blockIdx.x & 7) == 1 && u == 0)) *(uint4*)o = make_uint4(0x3F80u, 0, 0, 0);
    }
}

__device__ __forceinline__ void copy_x(int u, const __nv_bfloat16* x) {
    const int lane = tidx() & 31, T = u * 16 + (blockIdx.x >> 3), c = blockIdx.x & 7;
#pragma unroll 2
    for (int row = lane >> 3; row < 64; row += 4)
        g_X[(T * 8 + c) * 512 + ((lane & 7) >> 1) * 128 + (row >> 3) * 16 + (lane & 1) * 8 + (row & 7)] = __ldg((const uint4*)x + (T * 64 + row) * 64 + c * 8 + (lane & 7));
}
__device__ __forceinline__ void qkv_a_piece(float* acc, int k2, int L, int s, int w, uint32_t sbase) {
    const uint32_t bars = sbase + SM_MISC;
    const uint32_t a = sbase + (12 + 8 * w + 2 * k2) * PAGE;
    const uint64_t da = L == 0 ? mkdesc(a, 16, 1024, 1) : mkdesc(a, 128, 256, 0), db = mkdesc(sbase + k2 * 3 * PAGE, 4096, 512, 2);
    const int dks = L == 0 ? 2 : 128;
    mbar_wait(bars + 8 * (B_FULLA + w * 4 + k2), s ^ (L >> 1));
    wg_fence();
#pragma unroll
    for (int ks = 0; ks < 8; ks++) gemm96(acc, da + (ks >> 2) * (PAGE / 16) + dks * (ks & 3), db + (ks >> 2) * 768 + (ks & 3) * 64);
    wg_commit();
}
__device__ __forceinline__ void qkv_a_norm(const float* acc, float* y, float mu0, float mu1, float r0, float r1, const float* cs) {
    float2 cc[12];
    load_cs<12>(cc, cs);
#pragma unroll
    for (int i = 0; i < 12; i++) {
        const float f0 = i < 4 ? r0 * QSCALE : r0, f1 = i < 4 ? r1 * QSCALE : r1;
        y[4 * i] = (acc[4 * i] - mu0 * cc[i].x) * f0; y[4 * i + 1] = (acc[4 * i + 1] - mu0 * cc[i].y) * f0;
        y[4 * i + 2] = (acc[4 * i + 2] - mu1 * cc[i].x) * f1; y[4 * i + 3] = (acc[4 * i + 3] - mu1 * cc[i].y) * f1;
    }
}
__device__ __forceinline__ void qkv_a_store(const float* y, int what, int u, int s, int r, uint32_t* link) {
    const int h = 2 * (blockIdx.x & 15) + u, T = s * 16 + r;
    const float* q = y + 16 * what + 8 * u;
    if (what == 0) g_Q[(h * 32 + T) * 128 + (tidx() & 127)] = make_uint4(pack_f16(q[0], q[1]), pack_f16(q[2], q[3]), pack_f16(q[4], q[5]), pack_f16(q[6], q[7]));
    if (what == 1) store_max(g_kmax, store_k(q, h, s, r, link + 4 * u), h, T);
    if (what == 2) store_max(g_vmax, store_v(q, h, s, r), h, T);
}
__device__ __forceinline__ void qkv_a_phase(int L, int w, uint32_t sbase, float* cs, const Params& P) {
    const int r = 2 * (blockIdx.x >> 4) + w;
    const uint32_t bars = sbase + SM_MISC;
    const int tid = tidx() & 127;
    uint32_t link[8] = {0, 0, 0, 0, 0, 0, 0, 0};
    float acc[48], y[48];
    uint4 st0 = make_uint4(0, 0, 0, 0), st1 = st0;
    float mu0, mu1, r0, r1;
    zero_regs<48>(acc);
    if (L == 0) {
        uint4 xv[4];
        pre_load(xv, w, P.x);
        zero_regs<48>(y);
        pre_phase(xv, w);
#pragma unroll 1
        for (int k2 = 0; k2 < 4; k2++) {
            mbar_wait(bars + 8 * (B_FULLW + 2 * k2), 0);
            mbar_wait(bars + 8 * (B_FULLW + 2 * k2 + 1), 0);
            qkv_a_piece(acc, k2, 0, 0, w, sbase);
#pragma unroll
            for (int ks = 0; ks < 4; ks++) gemm96(y, mkdesc(sbase + SM_ONES, 0, 0, 0), mkdesc(sbase + k2 * 3 * PAGE + w * 12288, 4096, 512, 2) + ks * 64);
            wg_commit();
            wg_wait<1>();
            warp_arrive(bars + 8 * (B_EMPTYA + w * 4 + k2));
        }
        mbar_wait(bars + 8 * B_STAT, 0);
        st0 = ld_stats(r, 0); st1 = ld_stats(r, 1);
        wg_wait<0>();
        fence_regs<48>(acc); fence_regs<48>(y);
        put_cs<12>(cs + 96 * w, y);
        asm volatile("bar.sync 4, 256;" ::: "memory");
        if (w == 0 && tid < 96) cs[tid] += cs[96 + tid];
        asm volatile("bar.sync 4, 256;" ::: "memory");
    } else {
        mbar_wait(bars + 8 * B_STAT, 0);
        st0 = ld_stats(r, 0); st1 = ld_stats(r, 1);
#pragma unroll 1
        for (int k2 = 0; k2 < 4; k2++) {
            mbar_wait(bars + 8 * (B_FULLW + 2 * k2), 0);
            mbar_wait(bars + 8 * (B_FULLW + 2 * k2 + 1), 0);
            qkv_a_piece(acc, k2, L, 0, w, sbase);
            wg_wait<1>();
            if (k2 > 0) warp_arrive(bars + 8 * (B_EMPTYA + w * 4 + k2 - 1));
        }
        wg_wait<0>();
        fence_regs<48>(acc);
        warp_arrive(bars + 8 * (B_EMPTYA + w * 4 + 3));
    }
    row_stats(st0, mu0, r0); row_stats(st1, mu1, r1);
    qkv_a_norm(acc, y, mu0, mu1, r0, r1, cs);
    fence_regs<48>(y);
    zero_regs<48>(acc);
    qkv_a_store(y, 0, 0, 0, r, link); qkv_a_store(y, 2, 0, 0, r, link); qkv_a_store(y, 1, 0, 0, r, link);
    qkv_a_piece(acc, 0, L, 1, w, sbase);
    qkv_a_store(y, 0, 1, 0, r, link); qkv_a_store(y, 2, 1, 0, r, link); qkv_a_store(y, 1, 1, 0, r, link);
    nb_arrive(N_QKV, 288);
    mbar_wait(bars + 8 * (B_STAT + 1), 0);
    st0 = ld_stats(16 + r, 0); st1 = ld_stats(16 + r, 1);
#pragma unroll 1
    for (int k2 = 1; k2 < 4; k2++) qkv_a_piece(acc, k2, L, 1, w, sbase);
    row_stats(st0, mu0, r0); row_stats(st1, mu1, r1);
#pragma unroll
    for (int i = 0; i < 8; i++) link[i] = __shfl_down_sync(~0u, link[i], 12);
    wg_wait<0>();
    fence_regs<48>(acc);
    warp_arrive(bars + 8 * (B_QKVDONE + w));
    qkv_a_norm(acc, y, mu0, mu1, r0, r1, cs);
#pragma unroll
    for (int u = 0; u < 2; u++) { qkv_a_store(y, 2, u, 1, r, link); qkv_a_store(y, 1, u, 1, r, link); }
    nb_arrive(N_QKV + 1, 288);
    qkv_a_store(y, 0, 0, 1, r, link); qkv_a_store(y, 0, 1, 1, r, link);
    nb_arrive(N_QKV + 2, 288);
}
__device__ __forceinline__ void qkv_b_phase(int L, int w, uint32_t sbase, float* cs) {
    const int r = blockIdx.x >> 3, c = blockIdx.x & 7;
    const uint32_t bars = sbase + SM_MISC;
    if (L == 1) {
        if (w == 0) {
            float d[32], e[8];
            zero_regs<32>(d); zero_regs<8>(e);
            if (c < 2) mbar_wait(bars + 8 * B_FULLWKV, 0);
#pragma unroll 1
            for (int kc = 0; kc < 8; kc++) {
                mbar_wait(bars + 8 * (B_FULLW + kc), 1);
                wg_fence();
#pragma unroll
                for (int ks = 0; ks < 4; ks++) {
                    gemm64(d, mkdesc(sbase + SM_ONES, 0, 0, 0), mkdesc(sbase + kc * PAGE, PAGE, 1024, 1) + 128 * ks);
                    gemm16(e, mkdesc(sbase + SM_ONES, 0, 0, 0), mkdesc(sbase + 8 * PAGE + kc * 2048, 16, 256, 3) + 32 * ks);
                }
                wg_commit();
            }
            wg_wait<0>();
            fence_regs<32>(d); fence_regs<8>(e);
            put_cs<8>(cs + 192, d); put_cs<2>(cs + 256, e);
        }
        asm volatile("bar.sync 4, 256;" ::: "memory");
    }
    if (c < 2 && w == 1) { kv_extra(L, sbase, cs); warp_arrive(bars + 8 * B_QSM); return; }
    float2 cc[8];
    load_cs<8>(cc, cs + 192);
#pragma unroll 1
    for (int s = w; s <= (c < 2 ? 1 : w); s++) {
        float mu0, mu1, r0, r1, acc[32];
        mbar_wait(bars + 8 * (B_STAT + s), 1);
        const uint4 st0 = ld_stats(s * 16 + r, 0), st1 = ld_stats(s * 16 + r, 1);
        zero_regs<32>(acc);
        row_stats(st0, mu0, r0); row_stats(st1, mu1, r1);
        qkv_b_loop<false>(acc, L, s, sbase);
        if (s == 1 || c >= 2) warp_arrive(bars + 8 * (B_QKVDONE + w));
#pragma unroll
        for (int hh = 0; hh < 4; hh++) {
            float* y = acc + 8 * hh;
            normalise(y, cc + 2 * hh, mu0, mu1, r0 * QSCALE, r1 * QSCALE);
            asm volatile("st.shared.v4.u32 [%0], {%1, %2, %3, %4};" ::"r"(sbase + (26 + s) * PAGE + hh * 2048 + (tidx() & 127) * 16),
                         "r"(pack_f16(y[0], y[1])), "r"(pack_f16(y[2], y[3])), "r"(pack_f16(y[4], y[5])), "r"(pack_f16(y[6], y[7])) : "memory");
        }
    }
    warp_arrive(bars + 8 * B_QSM);
}

__device__ __forceinline__ void out_phase(int L, int w, uint32_t sbase, const Params& P) {
    const int par = L & 1, r = blockIdx.x >> 3, c = blockIdx.x & 7, T = w * 16 + r;
    const int tid = tidx() & 127, lane = tid & 31, warp = tid >> 5, g = lane >> 2, t = lane & 3;
    const uint32_t bars = sbase + SM_MISC;
    uint32_t xv[16];
    mbar_wait(bars + 8 * B_FULLWO, par);
    const int cm = (T * 8 + c) * 2048 + warp * 128 + lane;
#pragma unroll
    for (int i = 0; i < 16; i++) xv[i] = __ldcg((const uint32_t*)g_X + cm + (i >> 2) * 512 + ((i >> 1) & 1) * 32 + (i & 1) * 64);
    float acc[32];
    zero_regs<32>(acc);
#pragma unroll 1
    for (int k2 = 0; k2 < 4; k2++) {
        mbar_wait(bars + 8 * (B_FULLO + w * 4 + k2), par);
        const uint64_t da = mkdesc(sbase + (w * 12 + 2 * k2) * PAGE, 128, 256, 0);
        const uint64_t db = mkdesc(sbase + (20 + 2 * k2) * PAGE, PAGE, 1024, 1);
        wg_fence();
#pragma unroll
        for (int ks = 0; ks < 8; ks++) gemm64(acc, da + 128 * ks, db + 128 * ks);
        wg_commit();
    }
    wg_wait<0>();
    fence_regs<32>(acc);
    warp_arrive(bars + 8 * (B_OUTDONE + w));
#pragma unroll
    for (int i = 0; i < 16; i++) xv[i] = pack_bf16(acc[2 * i] + bf_lo(xv[i]), acc[2 * i + 1] + bf_hi(xv[i]));
    if (L == 3) {
        uint4* p = (uint4*)P.out + (T * 64 + warp * 16 + g) * 64 + c * 8 + t;
#pragma unroll
        for (int u = 0; u < 4; u++) {
            uint32_t a[4];
#pragma unroll
            for (int i = 0; i < 4; i++) a[i] = xv[2 * (4 * (u >> 1) + i) + (u & 1)];
#pragma unroll
            for (int m = 1; m <= 2; m <<= 1)
#pragma unroll
                for (int i = 0; i < 4; i++)
                    if (!(i & m)) {
                        const uint32_t x = __shfl_xor_sync(~0u, (t & m) ? a[i] : a[i + m], m);
                        if (t & m) a[i] = x; else a[i + m] = x;
                    }
            p[(u & 1) * 512 + (u >> 1) * 4] = make_uint4(a[0], a[1], a[2], a[3]);
        }
    } else {
        uint32_t* p = (uint32_t*)g_X + cm;
#pragma unroll
        for (int i = 0; i < 8; i++) { p[(i >> 1) * 512 + (i & 1) * 32] = xv[2 * i]; p[(i >> 1) * 512 + (i & 1) * 32 + 64] = xv[2 * i + 1]; }
        block_stats(xv, T, c);
        nb_arrive(N_OUT + w, 160);
    }
}

__device__ __forceinline__ void load_wa(int kc, uint32_t sbase, const Params& P) {
    const uint32_t bar = sbase + SM_MISC + 8 * (B_FULLW + kc);
    mbar_expect(bar, 12288);
#pragma unroll
    for (int i = 0; i < 3; i++) tma2d(sbase + kc * 12288 + i * 4096, &P.tmWqkv, i * 512 + (blockIdx.x & 15) * 32, kc * 64, bar);
}
__device__ __forceinline__ void load_x0(int st, int i, uint32_t sbase, const Params& P) {
    const uint32_t bar = sbase + SM_MISC + 8 * (B_FULLA + (i & 1) * 4 + (i >> 1)), dst = sbase + (12 + 8 * (i & 1) + (i & 6)) * PAGE;
    const int row = (st * 16 + 2 * (blockIdx.x >> 4) + (i & 1)) * 64;
    mbar_expect(bar, 2 * PAGE);
    tma2d(dst, &P.tmX, (i >> 1) * 128, row, bar);
    tma2d(dst + PAGE, &P.tmX, (i >> 1) * 128 + 64, row, bar);
}

__global__ void __launch_bounds__(384, 1) fused_kernel(const __grid_constant__ Params P) {
    extern __shared__ __align__(1024) uint8_t smem[];
    const uint32_t sbase = (uint32_t)__cvta_generic_to_shared(smem), bars = sbase + SM_MISC;
    const int wg = __shfl_sync(~0u, threadIdx.x >> 7, 0);
    if (wg == 2 && elect()) {
        const int sw = __shfl_sync(__activemask(), (threadIdx.x >> 5) & 3, threadIdx.x & 31);
#pragma unroll
        for (int i = 0; i < 13; i++) mbar_init(bars + 8 * (13 * sw + i), sw == 3 ? (i == 12 ? 8 : 4) : 1);
        if (sw == 0) mbar_init(bars + 8 * B_QY, 1);
        asm volatile("fence.mbarrier_init.release.cluster;" ::: "memory");
        asm volatile("fence.proxy.async.shared::cta;" ::: "memory");
    }
    if (threadIdx.x < 16) {
        *(uint2*)(smem + SM_ONES + threadIdx.x * 8) = make_uint2(0x3F803F80u, 0x3F803F80u);
        *(uint4*)(smem + SM_FILL + threadIdx.x * 16) = make_uint4(threadIdx.x < 8 ? 0x5e62u : 0xa202u, 0, 0, 0);
        asm volatile("fence.proxy.async.shared::cta;" ::: "memory");
    }
    __syncthreads();
    if (wg < 2) {
        asm volatile("setmaxnreg.inc.sync.aligned.u32 240;");
        float* cs = (float*)(smem + SM_CS);
#pragma unroll 1
        for (int L = 0; L < 4; L++) {
            if (L & 1) qkv_b_phase(L, wg, sbase, cs); else qkv_a_phase(L, wg, sbase, cs, P);
            attention(L, wg, sbase);
            out_phase(L, wg, sbase, P);
        }
    } else {
        asm volatile("setmaxnreg.dec.sync.aligned.u32 24;");
        uint32_t ep0;
        asm volatile("ld.volatile.global.u32 %0, [%1];" : "=r"(ep0) : "l"(&g_epoch[blockIdx.x]));
        if (elect()) {
            if (threadIdx.x < 288) {
#pragma unroll 1
                for (int kc = 0; kc < W0N; kc++) load_wa(kc, sbase, P);
            } else if (threadIdx.x < 320) {
#pragma unroll 1
                for (int i = 0; i < X0N; i++) load_x0(0, i, sbase, P);
            }
        }
        __syncwarp();
        const int role = __shfl_sync(~0u, (threadIdx.x >> 5) & 3, 0);
        const int r = blockIdx.x >> 3, c = blockIdx.x & 7, h = blockIdx.x >> 2, j = blockIdx.x & 3;
        const uint32_t ep = ep0 + 1;
        if (role == 0) {
#pragma unroll 1
            for (int L = 0; L < 4; L++) {
                const int par = L & 1;
#pragma unroll 1
                for (int st = 0; st < 2; st++) {
                    if (L > 0 && st == 0) { poll(C_X + L * 32 + (par ? r : 2 * (blockIdx.x >> 4) + (threadIdx.x & 1)), ep * 8, false); }
                    if (L > 0 && st == 1) mbar_wait(bars + 8 * (B_STAT + 1), par);
                    fence_async();
                    if (L > 0 && st == 0 && elect()) mbar_arrive(bars + 8 * B_STAT);
#pragma unroll 1
                    for (int i = L + st ? 0 : X0N; i < (par ? 4 : 8); i++) {
                        const int w = par ? st : i & 1, k2 = par ? i : i >> 1, T = st * 16 + (par ? r : 2 * (blockIdx.x >> 4) + w);
                        if (L > 0 && st == 0 && i == par) mbar_wait(bars + 8 * (B_OUTDONE + 1), par ^ 1);
                        if (!par && st) mbar_wait(bars + 8 * (B_EMPTYA + w * 4 + k2), L >> 1);
                        if (L == 0 && st == 0 && k2 >= XPACE) mbar_wait(bars + 8 * (B_FULLA + w * 4 + k2 - XPACE), 0);
                        const uint32_t bar = bars + 8 * (B_FULLA + w * 4 + k2), dst = sbase + ((par ? 10 : 12) + 8 * w + 2 * k2) * PAGE;
                        if (elect()) {
                            if (L == 0) load_x0(st, i, sbase, P);
                            else { mbar_expect(bar, 2 * PAGE); bulk_g2s(dst, (const uint8_t*)g_X + (size_t)(T * 8 + 2 * k2) * PAGE, 2 * PAGE, bar); }
                        }
                    }
                }
#pragma unroll 1
                for (int w = 0; w < 2; w++) {
                    nb_sync(N_E1 + w, w ? 320 : 288);
                    if (w == 0 && par == 0 && c < 2 && elect()) {
                        mbar_expect(bars + 8 * B_FULLWKV, 2 * PAGE);
                        tma2d(sbase + 8 * PAGE, c ? &P.tmWv : &P.tmWk, 0, 0, bars + 8 * B_FULLWKV);
                        tma2d(sbase + 9 * PAGE, c ? &P.tmWv : &P.tmWk, 0, 256, bars + 8 * B_FULLWKV);
                    }
                    poll(C_O + L * 32 + w * 16 + r, ep * 32, w == 0);
                    fence_async();
                    if (elect()) {
#pragma unroll
                        for (int i = 0; i < 4; i++) {
                            const uint32_t bar = bars + 8 * (B_FULLO + w * 4 + i);
                            mbar_expect(bar, 2 * PAGE);
                            bulk_g2s(sbase + (w * 12 + 2 * i) * PAGE, (const uint8_t*)g_O + (size_t)((w * 16 + r) * 8 + 2 * i) * PAGE, 2 * PAGE, bar);
                        }
                    }
                }
            }
        } else if (role == 1) {
#pragma unroll 1
            for (int L = 0; L < 4; L++) {
                const int par = L & 1;
                if (L > 0) mbar_wait(bars + 8 * B_OUTDONE, par ^ 1);
#pragma unroll 1
                for (int kc = L ? 0 : W0N; kc < 8; kc++) {
                    const uint32_t bar = bars + 8 * (B_FULLW + kc);
                    const int pace = L == 0 ? PACE : (par ? PACEB : PACEA);
                    if (kc >= pace) mbar_wait(bar - 8 * pace, par);
                    if (elect()) {
                        if (par) {
                            mbar_expect(bar, PAGE);
                            tma2d(sbase + kc * PAGE, &P.tmWq, c * 64, kc * 64, bar);
                        } else load_wa(kc, sbase, P);
                    }
                }
                if (L > 0) { poll(C_X + L * 32 + 16 + (par ? r : 2 * (blockIdx.x >> 4) + (threadIdx.x & 1)), ep * 8, false); if (elect()) mbar_arrive(bars + 8 * (B_STAT + 1)); }
                if (L == 0 && elect()) {
                    asm volatile("cp.async.bulk.prefetch.L2.global [%0], 4096;" ::"l"((const uint8_t*)P.woA + blockIdx.x * 4096) : "memory");
                    asm volatile("cp.async.bulk.prefetch.L2.global [%0], 4096;" ::"l"((const uint8_t*)P.wq + blockIdx.x * 4096) : "memory");
                    asm volatile("cp.async.bulk.prefetch.L2.global [%0], 4096;" ::"l"((const uint8_t*)P.woB + blockIdx.x * 4096) : "memory");
                }
                const uint8_t* kv = (const uint8_t*)g_KV + (size_t)(par ? 32 : h) * 16 * REC;
#pragma unroll 1
                for (int s = 0; s < 2; s++) {
                    poll(C_Q + L * 48 + s * 16 + (par ? c : h >> 1), ep * (par ? 32 : 8), false);
                    if (s == 0) { mbar_wait(bars + 8 * B_QKVDONE, par); mbar_wait(bars + 8 * (B_QKVDONE + 1), par); }
                    fence_async();
                    if (elect()) {
#pragma unroll
                        for (int i = 0; i < 4; i++) {
                            const int skip = (s | i) ? 0 : REC;
                            if (skip) {
                                mbar_expect(bars + 8 * B_QREADY, par ? REC : REC + PAGE);
                                if (!par) bulk_g2s(sbase + 26 * PAGE, &g_Q[(h * 32 + 4 * j) * 128], PAGE, bars + 8 * B_QREADY);
                                bulk_g2s(sbase, kv, REC, bars + 8 * B_QREADY);
                            }
                            mbar_expect(bars + 8 * (B_FULLKV + 4 * s + i), 2 * REC - skip);
                            bulk_g2s(sbase + (4 * s + i) * 2 * REC + skip, kv + (4 * s + i) * 2 * REC + skip, 2 * REC - skip, bars + 8 * (B_FULLKV + 4 * s + i));
                        }
                    }
                }
                if (!par) {
                    poll(C_Q + L * 48 + 32 + (h >> 1), ep * 8, true);
                    fence_async();
                    if (elect()) { mbar_expect(bars + 8 * B_QY, PAGE); bulk_g2s(sbase + 27 * PAGE, &g_Q[(h * 32 + 16 + 4 * j) * 128], PAGE, bars + 8 * B_QY); }
                }
                if (L == 0) { copy_x(0, P.x); copy_x(1, P.x); __syncwarp(); }
                nb_sync(N_QFREE, 288);
                if (elect()) {
                    mbar_expect(bars + 8 * B_FULLWO, 8 * PAGE);
#pragma unroll
                    for (int kc = 0; kc < 8; kc++) tma2d(sbase + (20 + kc) * PAGE, par ? &P.tmWoB : &P.tmWoA, c * 64, kc * 64, bars + 8 * B_FULLWO);
                }
                nb_sync(N_E2, 320);
            }
            if (elect()) g_epoch[blockIdx.x] = ep;
        } else {
            const int w = role - 2;
            if (w == 0) {
                nb_sync(N_O, 288);
                asm volatile("fence.release.gpu;" ::: "memory");
                if ((threadIdx.x & 31) < 2) bump(C_X + (threadIdx.x & 1) * 16 + r);
            }
            poll(C_X + w * 16 + 2 * (blockIdx.x >> 4) + (threadIdx.x & 1), ep * 8, false);
            if (elect()) mbar_arrive(bars + 8 * (B_STAT + w));
#pragma unroll 1
            for (int L = 0; L < 4; L++) {
                const int par = L & 1;
                if (!par) {
#pragma unroll 1
                    for (int e = w; e < 3; e += 2) { nb_sync(N_QKV + e, 288); if (elect()) publish(C_Q + L * 48 + e * 16 + (blockIdx.x & 15)); }
                } else if (w == 1 && c < 2) {
#pragma unroll 1
                    for (int e = 0; e < 2; e++) {
                        nb_sync(N_QKV + e, 160);
                        asm volatile("fence.release.gpu;" ::: "memory");
                        if ((threadIdx.x & 31) < 8) bump(C_Q + L * 48 + e * 16 + (threadIdx.x & 7));
                    }
                }
                mbar_nap(bars + 8 * (B_FULLKV + 7), par);
                mbar_nap(bars + 8 * (par ? B_QSM : B_QY), L >> 1);
                const uint32_t mask = unsafe_mask(par, w, sbase);
                if (elect()) { asm volatile("st.shared.u32 [%0], %1;" ::"r"(sbase + SM_MASK + 4 * w), "r"(mask) : "memory"); mbar_arrive(bars + 8 * (B_MASK + w)); }
#pragma unroll 1
                for (int p = w; p < 4; p += 2) {
                    nb_sync(N_O + p, 288);
                    asm volatile("fence.release.gpu;" ::: "memory");
                    if ((threadIdx.x & 31) < 2) bump(C_O + L * 32 + unit_tile(par, p, threadIdx.x & 1));
                }
                if (L < 3) { nb_sync(N_OUT + w, 160); if (elect()) publish(C_X + (L + 1) * 32 + w * 16 + r); }
            }
        }
    }
}

typedef CUresult (*EncodeFn)(CUtensorMap*, CUtensorMapDataType, cuuint32_t, void*, const cuuint64_t*, const cuuint64_t*, const cuuint32_t*,
                             const cuuint32_t*, CUtensorMapInterleave, CUtensorMapSwizzle, CUtensorMapL2promotion, CUtensorMapFloatOOBfill);
void make_map(EncodeFn enc, CUtensorMap* m, const void* p, int cols, int rows, int bc, int br, CUtensorMapSwizzle sw) {
    cuuint64_t dim[2] = {(cuuint64_t)cols, (cuuint64_t)rows}, str[1] = {(cuuint64_t)cols * 2};
    cuuint32_t box[2] = {(cuuint32_t)bc, (cuuint32_t)br}, es[2] = {1, 1};
    enc(m, CU_TENSOR_MAP_DATA_TYPE_BFLOAT16, 2, (void*)p, dim, str, box, es, CU_TENSOR_MAP_INTERLEAVE_NONE, sw, CU_TENSOR_MAP_L2_PROMOTION_L2_128B, CU_TENSOR_MAP_FLOAT_OOB_FILL_NONE);
}
}

extern "C" void kernel_launch(void* const* d_in, const int* in_sizes, int n_in, void* d_out, int out_size) {
    static Params P;
    if (P.x != d_in[0] || P.wqkv != d_in[1] || P.woA != d_in[2] || P.wq != d_in[4] || P.wk != d_in[5] || P.wv != d_in[6] || P.woB != d_in[7]) {
        void* fn = nullptr; cudaDriverEntryPointQueryResult qr;
        cudaGetDriverEntryPoint("cuTensorMapEncodeTiled", &fn, cudaEnableDefault, &qr);
        EncodeFn enc = (EncodeFn)fn;
        P.x = (const __nv_bfloat16*)d_in[0]; P.wqkv = (const __nv_bfloat16*)d_in[1]; P.woA = (const __nv_bfloat16*)d_in[2];
        P.wq = (const __nv_bfloat16*)d_in[4]; P.wk = (const __nv_bfloat16*)d_in[5]; P.wv = (const __nv_bfloat16*)d_in[6]; P.woB = (const __nv_bfloat16*)d_in[7];
        make_map(enc, &P.tmX, P.x, 512, 2048, 64, 64, CU_TENSOR_MAP_SWIZZLE_128B);
        make_map(enc, &P.tmWqkv, P.wqkv, 1536, 512, 32, 64, CU_TENSOR_MAP_SWIZZLE_64B);
        make_map(enc, &P.tmWoA, P.woA, 512, 512, 64, 64, CU_TENSOR_MAP_SWIZZLE_128B);
        make_map(enc, &P.tmWq, P.wq, 512, 512, 64, 64, CU_TENSOR_MAP_SWIZZLE_128B);
        make_map(enc, &P.tmWoB, P.woB, 512, 512, 64, 64, CU_TENSOR_MAP_SWIZZLE_128B);
        make_map(enc, &P.tmWk, P.wk, 16, 512, 16, 256, CU_TENSOR_MAP_SWIZZLE_32B);
        make_map(enc, &P.tmWv, P.wv, 16, 512, 16, 256, CU_TENSOR_MAP_SWIZZLE_32B);
        cudaFuncSetAttribute(fused_kernel, cudaFuncAttributeMaxDynamicSharedMemorySize, SM_TOTAL);
    }
    P.out = (__nv_bfloat16*)d_out;
    fused_kernel<<<NCTA, 384, SM_TOTAL>>>(P);
}
```
